```python
import torch

def _softmax(x, axis=-1):
    return torch.softmax(x, dim=axis)
def _gelu(x):
    return torch.nn.functional.gelu(x, approximate="tanh")
def _silu(x):
    return torch.nn.functional.silu(x)
def _sigmoid(x):
    return torch.sigmoid(x)
def _layernorm(x, axis=-1, eps=1e-5):
    m = x.mean(dim=axis, keepdim=True)
    v = x.var(dim=axis, keepdim=True, unbiased=False)
    return (x - m) / torch.sqrt(v + eps)
def _scatter_add(tgt, idx, src, axis=0):
    return tgt.clone().index_add_(axis, idx, src)
def _segment_sum(src, seg, n):
    out = torch.zeros((n,) + src.shape[1:], dtype=src.dtype)
    return out.index_add_(0, seg, src)
def _pad(x, pw):
    flat = tuple(v for pair in reversed(pw) for v in pair)
    return torch.nn.functional.pad(x, flat)

kernel_name = 'parallel_sum__ssm_conv_h3__glu_gated_geglu__prompt'

def setup_inputs():

    _w = (lambda a: (lambda t: t.to(torch.bfloat16) if t.is_floating_point() else t)(torch.as_tensor(a)))
    def _A_setup():
        B, S, D = 1, 2048, 512
        ks = 4
        return {
            "q": _w((lambda *s: torch.randn(*s, dtype=torch.bfloat16) * 0.05)(B, S, D)),
            "k": _w((lambda *s: torch.randn(*s, dtype=torch.bfloat16) * 0.2)(B, S, D)),
            "v": _w((lambda *s: torch.randn(*s, dtype=torch.bfloat16) * 0.2)(B, S, D)),
            "shift_k": _w((lambda *s: torch.randn(*s, dtype=torch.bfloat16) * 0.2)(D, ks) * 0.5),
            "ssm_k": _w((lambda *s: torch.randn(*s, dtype=torch.bfloat16) * 0.4)(D, S) * (1.0 / S ** 0.5)),
            "ssm_D": _w((lambda *s: torch.randn(*s, dtype=torch.bfloat16) * 0.2)(D)),
        }
    _A_in = _A_setup()

    def _B_setup():
        B, S, Dm, Df = 1, 2048, 512, 1792
        return {
            "x": _w((lambda *s: torch.randn(*s, dtype=torch.bfloat16) * 0.05)(B, S, Dm)),
            "w_gate": _w((lambda *s: torch.randn(*s, dtype=torch.bfloat16) * 0.4)(Dm, Df) * (Dm ** -0.5)),
            "w_up": _w((lambda *s: torch.randn(*s, dtype=torch.bfloat16) * 0.4)(Dm, Df) * (Dm ** -0.5)),
            "w_down": _w((lambda *s: torch.randn(*s, dtype=torch.bfloat16) * 0.4)(Df, Dm) * (Df ** -0.5)),
        }
    _B_in = _B_setup()

    return {
        "A_q": _A_in["q"],
        "A_k": _A_in["k"],
        "A_v": _A_in["v"],
        "A_shift_k": _A_in["shift_k"],
        "A_ssm_k": _A_in["ssm_k"],
        "A_ssm_D": _A_in["ssm_D"],
        "B_x": _B_in["x"],
        "B_w_gate": _B_in["w_gate"],
        "B_w_up": _B_in["w_up"],
        "B_w_down": _B_in["w_down"],
    }

def reference(A_q, A_k, A_v, A_shift_k, A_ssm_k, A_ssm_D, B_x, B_w_gate, B_w_up, B_w_down):
    def _A_ref(q, k, v, shift_k, ssm_k, ssm_D):
        B, S, D = q.shape
        ks = shift_k.shape[-1]
        k_pad = _pad(k, ((0, 0), (ks - 1, 0), (0, 0)))
        k_shift = torch.zeros_like(k)
        for t in range(ks):
            k_shift = k_shift + k_pad[:, t:t + S, :] * shift_k[:, ks - 1 - t][None, None, :]
        kv = k_shift * v
        L = 2 * S
        kv_pad = _pad(kv, ((0, 0), (0, S), (0, 0)))
        kf_pad = _pad(ssm_k, ((0, 0), (0, S)))
        kv_f = (lambda x, axes=(-2,-1): torch.fft.rfft2(x.float(), dim=axes))(kv_pad[:, None, :, :], axes=(1, 2))
        kf_f = (lambda x, axes=(-2,-1): torch.fft.rfft2(x.float(), dim=axes))(kf_pad[:, None, :], axes=(1, 2))
        kf_f = (lambda x, *d: x.permute(*d))(kf_f, 1, 2, 0)
        y_f = kv_f * kf_f[None, :, :, :]
        y = (lambda x, s, axes=(-2,-1): torch.fft.irfft2(x, s=s, dim=axes).to(torch.bfloat16))(y_f, (1, L), axes=(1, 2))[:, 0, :S, :]
        y = y + kv * ssm_D[None, None, :]
        return q * y

    def _B_ref(x, w_gate, w_up, w_down):
        g = torch.einsum("bsd,df->bsf", x, w_gate)
        u = torch.einsum("bsd,df->bsf", x, w_up)
        h = _gelu(g) * u
        return torch.einsum("bsf,fd->bsd", h, w_down)

    x = A_q
    xn = _layernorm(x, axis=-1)
    return x + _A_ref(xn, A_k, A_v, A_shift_k, A_ssm_k, A_ssm_D) + _B_ref(xn, B_w_gate, B_w_up, B_w_down)
```

```cpp
#include <cuda_runtime.h>
#include <cuda_bf16.h>
#include <cuda.h>
#include <stdint.h>

__device__ __forceinline__ void wgmma_ss_n128(float* d, uint64_t da, uint64_t db, int sd) {
  asm volatile("{\n.reg .pred p;\nsetp.ne.b32 p, %66, 0;\n"
    "wgmma.mma_async.sync.aligned.m64n128k16.f32.bf16.bf16 {%0, %1, %2, %3, %4, %5, %6, %7, %8, %9, %10, %11, %12, %13, %14, %15, %16, %17, %18, %19, %20, %21, %22, %23, %24, %25, %26, %27, "
    "%28, %29, %30, %31, %32, %33, %34, %35, %36, %37, %38, %39, %40, %41, %42, %43, %44, %45, %46, %47, %48, %49, %50, %51, %52, %53, "
    "%54, %55, %56, %57, %58, %59, %60, %61, %62, %63}, %64, %65, p, 1, 1, 0, 1;\n}\n"
    : "+f"(d[0]), "+f"(d[1]), "+f"(d[2]), "+f"(d[3]), "+f"(d[4]), "+f"(d[5]), "+f"(d[6]), "+f"(d[7]), "+f"(d[8]), "+f"(d[9]), "+f"(d[10]),
      "+f"(d[11]), "+f"(d[12]), "+f"(d[13]), "+f"(d[14]), "+f"(d[15]), "+f"(d[16]), "+f"(d[17]), "+f"(d[18]), "+f"(d[19]), "+f"(d[20]),
      "+f"(d[21]), "+f"(d[22]), "+f"(d[23]), "+f"(d[24]), "+f"(d[25]), "+f"(d[26]), "+f"(d[27]), "+f"(d[28]), "+f"(d[29]), "+f"(d[30]),
      "+f"(d[31]), "+f"(d[32]), "+f"(d[33]), "+f"(d[34]), "+f"(d[35]), "+f"(d[36]), "+f"(d[37]), "+f"(d[38]), "+f"(d[39]), "+f"(d[40]),
      "+f"(d[41]), "+f"(d[42]), "+f"(d[43]), "+f"(d[44]), "+f"(d[45]), "+f"(d[46]), "+f"(d[47]), "+f"(d[48]), "+f"(d[49]), "+f"(d[50]),
      "+f"(d[51]), "+f"(d[52]), "+f"(d[53]), "+f"(d[54]), "+f"(d[55]), "+f"(d[56]), "+f"(d[57]), "+f"(d[58]), "+f"(d[59]), "+f"(d[60]),
      "+f"(d[61]), "+f"(d[62]), "+f"(d[63])
    : "l"(da), "l"(db), "r"(sd));
}
template<int TB> __device__ __forceinline__ void wgmma_rs_init_n128(float* d, uint32_t a0, uint32_t a1, uint32_t a2, uint32_t a3, uint64_t db) {
  asm volatile("{\n.reg .pred p;\nsetp.ne.b32 p, 0, 0;\n"
    "wgmma.mma_async.sync.aligned.m64n128k16.f32.bf16.bf16 {%0, %1, %2, %3, %4, %5, %6, %7, %8, %9, %10, %11, %12, %13, %14, %15, %16, %17, %18, %19, %20, %21, %22, %23, %24, %25, %26, %27, "
    "%28, %29, %30, %31, %32, %33, %34, %35, %36, %37, %38, %39, %40, %41, %42, %43, %44, %45, %46, %47, %48, %49, %50, %51, %52, %53, "
    "%54, %55, %56, %57, %58, %59, %60, %61, %62, %63}, {%64, %65, %66, %67}, %68, p, 1, 1, %69;\n}\n"
    : "=f"(d[0]), "=f"(d[1]), "=f"(d[2]), "=f"(d[3]), "=f"(d[4]), "=f"(d[5]), "=f"(d[6]), "=f"(d[7]), "=f"(d[8]), "=f"(d[9]), "=f"(d[10]),
      "=f"(d[11]), "=f"(d[12]), "=f"(d[13]), "=f"(d[14]), "=f"(d[15]), "=f"(d[16]), "=f"(d[17]), "=f"(d[18]), "=f"(d[19]), "=f"(d[20]),
      "=f"(d[21]), "=f"(d[22]), "=f"(d[23]), "=f"(d[24]), "=f"(d[25]), "=f"(d[26]), "=f"(d[27]), "=f"(d[28]), "=f"(d[29]), "=f"(d[30]),
      "=f"(d[31]), "=f"(d[32]), "=f"(d[33]), "=f"(d[34]), "=f"(d[35]), "=f"(d[36]), "=f"(d[37]), "=f"(d[38]), "=f"(d[39]), "=f"(d[40]),
      "=f"(d[41]), "=f"(d[42]), "=f"(d[43]), "=f"(d[44]), "=f"(d[45]), "=f"(d[46]), "=f"(d[47]), "=f"(d[48]), "=f"(d[49]), "=f"(d[50]),
      "=f"(d[51]), "=f"(d[52]), "=f"(d[53]), "=f"(d[54]), "=f"(d[55]), "=f"(d[56]), "=f"(d[57]), "=f"(d[58]), "=f"(d[59]), "=f"(d[60]),
      "=f"(d[61]), "=f"(d[62]), "=f"(d[63])
    : "r"(a0), "r"(a1), "r"(a2), "r"(a3), "l"(db), "n"(TB));
}
template<int TB> __device__ __forceinline__ void wgmma_rs_n128(float* d, uint32_t a0, uint32_t a1, uint32_t a2, uint32_t a3, uint64_t db, int sd) {
  asm volatile("{\n.reg .pred p;\nsetp.ne.b32 p, %69, 0;\n"
    "wgmma.mma_async.sync.aligned.m64n128k16.f32.bf16.bf16 {%0, %1, %2, %3, %4, %5, %6, %7, %8, %9, %10, %11, %12, %13, %14, %15, %16, %17, %18, %19, %20, %21, %22, %23, %24, %25, %26, %27, "
    "%28, %29, %30, %31, %32, %33, %34, %35, %36, %37, %38, %39, %40, %41, %42, %43, %44, %45, %46, %47, %48, %49, %50, %51, %52, %53, "
    "%54, %55, %56, %57, %58, %59, %60, %61, %62, %63}, {%64, %65, %66, %67}, %68, p, 1, 1, %70;\n}\n"
    : "+f"(d[0]), "+f"(d[1]), "+f"(d[2]), "+f"(d[3]), "+f"(d[4]), "+f"(d[5]), "+f"(d[6]), "+f"(d[7]), "+f"(d[8]), "+f"(d[9]), "+f"(d[10]),
      "+f"(d[11]), "+f"(d[12]), "+f"(d[13]), "+f"(d[14]), "+f"(d[15]), "+f"(d[16]), "+f"(d[17]), "+f"(d[18]), "+f"(d[19]), "+f"(d[20]),
      "+f"(d[21]), "+f"(d[22]), "+f"(d[23]), "+f"(d[24]), "+f"(d[25]), "+f"(d[26]), "+f"(d[27]), "+f"(d[28]), "+f"(d[29]), "+f"(d[30]),
      "+f"(d[31]), "+f"(d[32]), "+f"(d[33]), "+f"(d[34]), "+f"(d[35]), "+f"(d[36]), "+f"(d[37]), "+f"(d[38]), "+f"(d[39]), "+f"(d[40]),
      "+f"(d[41]), "+f"(d[42]), "+f"(d[43]), "+f"(d[44]), "+f"(d[45]), "+f"(d[46]), "+f"(d[47]), "+f"(d[48]), "+f"(d[49]), "+f"(d[50]),
      "+f"(d[51]), "+f"(d[52]), "+f"(d[53]), "+f"(d[54]), "+f"(d[55]), "+f"(d[56]), "+f"(d[57]), "+f"(d[58]), "+f"(d[59]), "+f"(d[60]),
      "+f"(d[61]), "+f"(d[62]), "+f"(d[63])
    : "r"(a0), "r"(a1), "r"(a2), "r"(a3), "l"(db), "r"(sd), "n"(TB));
}
__device__ __forceinline__ void conv_block_0_14(float* e, const uint32_t* a, uint64_t db) {
  asm volatile("{\n.reg .pred p0, p1;\n.reg .b64 d;\nsetp.ne.b32 p0, 0, 0;\nsetp.eq.b32 p1, 0, 0;\n"
    "add.s64 d, %184, 0;\n"
    "wgmma.mma_async.sync.aligned.m64n256k16.f32.bf16.bf16 {%0, %1, %2, %3, %4, %5, %6, %7, %8, %9, %10, %11, %12, %13, %14, %15, %16, %17, %18, %19, %20, %21, %22, %23, %24, %25, %26, %27, "
    "%28, %29, %30, %31, %32, %33, %34, %35, %36, %37, %38, %39, %40, %41, %42, %43, %44, %45, %46, %47, %48, %49, %50, %51, %52, %53, "
    "%54, %55, %56, %57, %58, %59, %60, %61, %62, %63, %64, %65, %66, %67, %68, %69, %70, %71, %72, %73, %74, %75, %76, %77, %78, %79, "
    "%80, %81, %82, %83, %84, %85, %86, %87, %88, %89, %90, %91, %92, %93, %94, %95, %96, %97, %98, %99, %100, %101, %102, %103, %104, "
    "%105, %106, %107, %108, %109, %110, %111, %112, %113, %114, %115, %116, %117, %118, %119, %120, %121, %122, %123, %124, %125, "
    "%126, %127}, {%128, %129, %130, %131}, d, p0, 1, 1, 0;\n"
    "add.s64 d, %184, 240;\n"
    "wgmma.mma_async.sync.aligned.m64n16k16.f32.bf16.bf16 {%0, %1, %2, %3, %4, %5, %6, %7}, {%132, %133, %134, %135}, d, p1, 1, 1, 0;\n"
    "add.s64 d, %184, 224;\n"
    "wgmma.mma_async.sync.aligned.m64n32k16.f32.bf16.bf16 {%0, %1, %2, %3, %4, %5, %6, %7, %8, %9, %10, %11, %12, %13, %14, %15}, {%136, %137, %138, %139}, d, p1, 1, 1, 0;\n"
    "add.s64 d, %184, 208;\n"
    "wgmma.mma_async.sync.aligned.m64n48k16.f32.bf16.bf16 {%0, %1, %2, %3, %4, %5, %6, %7, %8, %9, %10, %11, %12, %13, %14, %15, %16, %17, %18, %19, %20, %21, %22, %23}, {%140, %141, %142, %143}, d, p1, 1, 1, 0;\n"
    "add.s64 d, %184, 192;\n"
    "wgmma.mma_async.sync.aligned.m64n64k16.f32.bf16.bf16 {%0, %1, %2, %3, %4, %5, %6, %7, %8, %9, %10, %11, %12, %13, %14, %15, %16, %17, %18, %19, %20, %21, %22, %23, %24, %25, %26, %27, "
    "%28, %29, %30, %31}, {%144, %145, %146, %147}, d, p1, 1, 1, 0;\n"
    "add.s64 d, %184, 176;\n"
    "wgmma.mma_async.sync.aligned.m64n80k16.f32.bf16.bf16 {%0, %1, %2, %3, %4, %5, %6, %7, %8, %9, %10, %11, %12, %13, %14, %15, %16, %17, %18, %19, %20, %21, %22, %23, %24, %25, %26, %27, "
    "%28, %29, %30, %31, %32, %33, %34, %35, %36, %37, %38, %39}, {%148, %149, %150, %151}, d, p1, 1, 1, 0;\n"
    "add.s64 d, %184, 160;\n"
    "wgmma.mma_async.sync.aligned.m64n96k16.f32.bf16.bf16 {%0, %1, %2, %3, %4, %5, %6, %7, %8, %9, %10, %11, %12, %13, %14, %15, %16, %17, %18, %19, %20, %21, %22, %23, %24, %25, %26, %27, "
    "%28, %29, %30, %31, %32, %33, %34, %35, %36, %37, %38, %39, %40, %41, %42, %43, %44, %45, %46, %47}, {%152, %153, %154, %155}, d, p1, 1, 1, 0;\n"
    "add.s64 d, %184, 144;\n"
    "wgmma.mma_async.sync.aligned.m64n112k16.f32.bf16.bf16 {%0, %1, %2, %3, %4, %5, %6, %7, %8, %9, %10, %11, %12, %13, %14, %15, %16, %17, %18, %19, %20, %21, %22, %23, %24, %25, %26, %27, "
    "%28, %29, %30, %31, %32, %33, %34, %35, %36, %37, %38, %39, %40, %41, %42, %43, %44, %45, %46, %47, %48, %49, %50, %51, %52, %53, "
    "%54, %55}, {%156, %157, %158, %159}, d, p1, 1, 1, 0;\n"
    "add.s64 d, %184, 128;\n"
    "wgmma.mma_async.sync.aligned.m64n128k16.f32.bf16.bf16 {%0, %1, %2, %3, %4, %5, %6, %7, %8, %9, %10, %11, %12, %13, %14, %15, %16, %17, %18, %19, %20, %21, %22, %23, %24, %25, %26, %27, "
    "%28, %29, %30, %31, %32, %33, %34, %35, %36, %37, %38, %39, %40, %41, %42, %43, %44, %45, %46, %47, %48, %49, %50, %51, %52, %53, "
    "%54, %55, %56, %57, %58, %59, %60, %61, %62, %63}, {%160, %161, %162, %163}, d, p1, 1, 1, 0;\n"
    "add.s64 d, %184, 112;\n"
    "wgmma.mma_async.sync.aligned.m64n144k16.f32.bf16.bf16 {%0, %1, %2, %3, %4, %5, %6, %7, %8, %9, %10, %11, %12, %13, %14, %15, %16, %17, %18, %19, %20, %21, %22, %23, %24, %25, %26, %27, "
    "%28, %29, %30, %31, %32, %33, %34, %35, %36, %37, %38, %39, %40, %41, %42, %43, %44, %45, %46, %47, %48, %49, %50, %51, %52, %53, "
    "%54, %55, %56, %57, %58, %59, %60, %61, %62, %63, %64, %65, %66, %67, %68, %69, %70, %71}, {%164, %165, %166, %167}, d, p1, 1, 1, 0;\n"
    "add.s64 d, %184, 96;\n"
    "wgmma.mma_async.sync.aligned.m64n160k16.f32.bf16.bf16 {%0, %1, %2, %3, %4, %5, %6, %7, %8, %9, %10, %11, %12, %13, %14, %15, %16, %17, %18, %19, %20, %21, %22, %23, %24, %25, %26, %27, "
    "%28, %29, %30, %31, %32, %33, %34, %35, %36, %37, %38, %39, %40, %41, %42, %43, %44, %45, %46, %47, %48, %49, %50, %51, %52, %53, "
    "%54, %55, %56, %57, %58, %59, %60, %61, %62, %63, %64, %65, %66, %67, %68, %69, %70, %71, %72, %73, %74, %75, %76, %77, %78, %79}, {%168, %169, %170, %171}, d, p1, 1, 1, 0;\n"
    "add.s64 d, %184, 80;\n"
    "wgmma.mma_async.sync.aligned.m64n176k16.f32.bf16.bf16 {%0, %1, %2, %3, %4, %5, %6, %7, %8, %9, %10, %11, %12, %13, %14, %15, %16, %17, %18, %19, %20, %21, %22, %23, %24, %25, %26, %27, "
    "%28, %29, %30, %31, %32, %33, %34, %35, %36, %37, %38, %39, %40, %41, %42, %43, %44, %45, %46, %47, %48, %49, %50, %51, %52, %53, "
    "%54, %55, %56, %57, %58, %59, %60, %61, %62, %63, %64, %65, %66, %67, %68, %69, %70, %71, %72, %73, %74, %75, %76, %77, %78, %79, "
    "%80, %81, %82, %83, %84, %85, %86, %87}, {%172, %173, %174, %175}, d, p1, 1, 1, 0;\n"
    "add.s64 d, %184, 64;\n"
    "wgmma.mma_async.sync.aligned.m64n192k16.f32.bf16.bf16 {%0, %1, %2, %3, %4, %5, %6, %7, %8, %9, %10, %11, %12, %13, %14, %15, %16, %17, %18, %19, %20, %21, %22, %23, %24, %25, %26, %27, "
    "%28, %29, %30, %31, %32, %33, %34, %35, %36, %37, %38, %39, %40, %41, %42, %43, %44, %45, %46, %47, %48, %49, %50, %51, %52, %53, "
    "%54, %55, %56, %57, %58, %59, %60, %61, %62, %63, %64, %65, %66, %67, %68, %69, %70, %71, %72, %73, %74, %75, %76, %77, %78, %79, "
    "%80, %81, %82, %83, %84, %85, %86, %87, %88, %89, %90, %91, %92, %93, %94, %95}, {%176, %177, %178, %179}, d, p1, 1, 1, 0;\n"
    "add.s64 d, %184, 48;\n"
    "wgmma.mma_async.sync.aligned.m64n208k16.f32.bf16.bf16 {%0, %1, %2, %3, %4, %5, %6, %7, %8, %9, %10, %11, %12, %13, %14, %15, %16, %17, %18, %19, %20, %21, %22, %23, %24, %25, %26, %27, "
    "%28, %29, %30, %31, %32, %33, %34, %35, %36, %37, %38, %39, %40, %41, %42, %43, %44, %45, %46, %47, %48, %49, %50, %51, %52, %53, "
    "%54, %55, %56, %57, %58, %59, %60, %61, %62, %63, %64, %65, %66, %67, %68, %69, %70, %71, %72, %73, %74, %75, %76, %77, %78, %79, "
    "%80, %81, %82, %83, %84, %85, %86, %87, %88, %89, %90, %91, %92, %93, %94, %95, %96, %97, %98, %99, %100, %101, %102, %103}, {%180, %181, %182, %183}, d, p1, 1, 1, 0;\n"
    "}\n"
    : "=f"(e[0]), "=f"(e[1]), "=f"(e[2]), "=f"(e[3]), "=f"(e[4]), "=f"(e[5]), "=f"(e[6]), "=f"(e[7]), "=f"(e[8]), "=f"(e[9]), "=f"(e[10]),
      "=f"(e[11]), "=f"(e[12]), "=f"(e[13]), "=f"(e[14]), "=f"(e[15]), "=f"(e[16]), "=f"(e[17]), "=f"(e[18]), "=f"(e[19]), "=f"(e[20]),
      "=f"(e[21]), "=f"(e[22]), "=f"(e[23]), "=f"(e[24]), "=f"(e[25]), "=f"(e[26]), "=f"(e[27]), "=f"(e[28]), "=f"(e[29]), "=f"(e[30]),
      "=f"(e[31]), "=f"(e[32]), "=f"(e[33]), "=f"(e[34]), "=f"(e[35]), "=f"(e[36]), "=f"(e[37]), "=f"(e[38]), "=f"(e[39]), "=f"(e[40]),
      "=f"(e[41]), "=f"(e[42]), "=f"(e[43]), "=f"(e[44]), "=f"(e[45]), "=f"(e[46]), "=f"(e[47]), "=f"(e[48]), "=f"(e[49]), "=f"(e[50]),
      "=f"(e[51]), "=f"(e[52]), "=f"(e[53]), "=f"(e[54]), "=f"(e[55]), "=f"(e[56]), "=f"(e[57]), "=f"(e[58]), "=f"(e[59]), "=f"(e[60]),
      "=f"(e[61]), "=f"(e[62]), "=f"(e[63]), "=f"(e[64]), "=f"(e[65]), "=f"(e[66]), "=f"(e[67]), "=f"(e[68]), "=f"(e[69]), "=f"(e[70]),
      "=f"(e[71]), "=f"(e[72]), "=f"(e[73]), "=f"(e[74]), "=f"(e[75]), "=f"(e[76]), "=f"(e[77]), "=f"(e[78]), "=f"(e[79]), "=f"(e[80]),
      "=f"(e[81]), "=f"(e[82]), "=f"(e[83]), "=f"(e[84]), "=f"(e[85]), "=f"(e[86]), "=f"(e[87]), "=f"(e[88]), "=f"(e[89]), "=f"(e[90]),
      "=f"(e[91]), "=f"(e[92]), "=f"(e[93]), "=f"(e[94]), "=f"(e[95]), "=f"(e[96]), "=f"(e[97]), "=f"(e[98]), "=f"(e[99]), "=f"(e[100]),
      "=f"(e[101]), "=f"(e[102]), "=f"(e[103]), "=f"(e[104]), "=f"(e[105]), "=f"(e[106]), "=f"(e[107]), "=f"(e[108]), "=f"(e[109]), "=f"(e[110]),
      "=f"(e[111]), "=f"(e[112]), "=f"(e[113]), "=f"(e[114]), "=f"(e[115]), "=f"(e[116]), "=f"(e[117]), "=f"(e[118]), "=f"(e[119]), "=f"(e[120]),
      "=f"(e[121]), "=f"(e[122]), "=f"(e[123]), "=f"(e[124]), "=f"(e[125]), "=f"(e[126]), "=f"(e[127])
    : "r"(a[0]), "r"(a[1]), "r"(a[2]), "r"(a[3]), "r"(a[4]), "r"(a[5]), "r"(a[6]), "r"(a[7]), "r"(a[8]), "r"(a[9]), "r"(a[10]), "r"(a[11]),
      "r"(a[12]), "r"(a[13]), "r"(a[14]), "r"(a[15]), "r"(a[16]), "r"(a[17]), "r"(a[18]), "r"(a[19]), "r"(a[20]), "r"(a[21]), "r"(a[22]),
      "r"(a[23]), "r"(a[24]), "r"(a[25]), "r"(a[26]), "r"(a[27]), "r"(a[28]), "r"(a[29]), "r"(a[30]), "r"(a[31]), "r"(a[32]), "r"(a[33]),
      "r"(a[34]), "r"(a[35]), "r"(a[36]), "r"(a[37]), "r"(a[38]), "r"(a[39]), "r"(a[40]), "r"(a[41]), "r"(a[42]), "r"(a[43]), "r"(a[44]),
      "r"(a[45]), "r"(a[46]), "r"(a[47]), "r"(a[48]), "r"(a[49]), "r"(a[50]), "r"(a[51]), "r"(a[52]), "r"(a[53]), "r"(a[54]), "r"(a[55]), "l"(db));
}
__device__ __forceinline__ void conv_block_14_16(float* e, const uint32_t* a, uint64_t db) {
  asm volatile("{\n.reg .pred p0, p1;\n.reg .b64 d;\nsetp.ne.b32 p0, 0, 0;\nsetp.eq.b32 p1, 0, 0;\n"
    "add.s64 d, %136, 32;\n"
    "wgmma.mma_async.sync.aligned.m64n224k16.f32.bf16.bf16 {%0, %1, %2, %3, %4, %5, %6, %7, %8, %9, %10, %11, %12, %13, %14, %15, %16, %17, %18, %19, %20, %21, %22, %23, %24, %25, %26, %27, "
    "%28, %29, %30, %31, %32, %33, %34, %35, %36, %37, %38, %39, %40, %41, %42, %43, %44, %45, %46, %47, %48, %49, %50, %51, %52, %53, "
    "%54, %55, %56, %57, %58, %59, %60, %61, %62, %63, %64, %65, %66, %67, %68, %69, %70, %71, %72, %73, %74, %75, %76, %77, %78, %79, "
    "%80, %81, %82, %83, %84, %85, %86, %87, %88, %89, %90, %91, %92, %93, %94, %95, %96, %97, %98, %99, %100, %101, %102, %103, %104, "
    "%105, %106, %107, %108, %109, %110, %111}, {%128, %129, %130, %131}, d, p1, 1, 1, 0;\n"
    "add.s64 d, %136, 16;\n"
    "wgmma.mma_async.sync.aligned.m64n240k16.f32.bf16.bf16 {%0, %1, %2, %3, %4, %5, %6, %7, %8, %9, %10, %11, %12, %13, %14, %15, %16, %17, %18, %19, %20, %21, %22, %23, %24, %25, %26, %27, "
    "%28, %29, %30, %31, %32, %33, %34, %35, %36, %37, %38, %39, %40, %41, %42, %43, %44, %45, %46, %47, %48, %49, %50, %51, %52, %53, "
    "%54, %55, %56, %57, %58, %59, %60, %61, %62, %63, %64, %65, %66, %67, %68, %69, %70, %71, %72, %73, %74, %75, %76, %77, %78, %79, "
    "%80, %81, %82, %83, %84, %85, %86, %87, %88, %89, %90, %91, %92, %93, %94, %95, %96, %97, %98, %99, %100, %101, %102, %103, %104, "
    "%105, %106, %107, %108, %109, %110, %111, %112, %113, %114, %115, %116, %117, %118, %119}, {%132, %133, %134, %135}, d, p1, 1, 1, 0;\n"
    "}\n"
    : "+f"(e[0]), "+f"(e[1]), "+f"(e[2]), "+f"(e[3]), "+f"(e[4]), "+f"(e[5]), "+f"(e[6]), "+f"(e[7]), "+f"(e[8]), "+f"(e[9]), "+f"(e[10]),
      "+f"(e[11]), "+f"(e[12]), "+f"(e[13]), "+f"(e[14]), "+f"(e[15]), "+f"(e[16]), "+f"(e[17]), "+f"(e[18]), "+f"(e[19]), "+f"(e[20]),
      "+f"(e[21]), "+f"(e[22]), "+f"(e[23]), "+f"(e[24]), "+f"(e[25]), "+f"(e[26]), "+f"(e[27]), "+f"(e[28]), "+f"(e[29]), "+f"(e[30]),
      "+f"(e[31]), "+f"(e[32]), "+f"(e[33]), "+f"(e[34]), "+f"(e[35]), "+f"(e[36]), "+f"(e[37]), "+f"(e[38]), "+f"(e[39]), "+f"(e[40]),
      "+f"(e[41]), "+f"(e[42]), "+f"(e[43]), "+f"(e[44]), "+f"(e[45]), "+f"(e[46]), "+f"(e[47]), "+f"(e[48]), "+f"(e[49]), "+f"(e[50]),
      "+f"(e[51]), "+f"(e[52]), "+f"(e[53]), "+f"(e[54]), "+f"(e[55]), "+f"(e[56]), "+f"(e[57]), "+f"(e[58]), "+f"(e[59]), "+f"(e[60]),
      "+f"(e[61]), "+f"(e[62]), "+f"(e[63]), "+f"(e[64]), "+f"(e[65]), "+f"(e[66]), "+f"(e[67]), "+f"(e[68]), "+f"(e[69]), "+f"(e[70]),
      "+f"(e[71]), "+f"(e[72]), "+f"(e[73]), "+f"(e[74]), "+f"(e[75]), "+f"(e[76]), "+f"(e[77]), "+f"(e[78]), "+f"(e[79]), "+f"(e[80]),
      "+f"(e[81]), "+f"(e[82]), "+f"(e[83]), "+f"(e[84]), "+f"(e[85]), "+f"(e[86]), "+f"(e[87]), "+f"(e[88]), "+f"(e[89]), "+f"(e[90]),
      "+f"(e[91]), "+f"(e[92]), "+f"(e[93]), "+f"(e[94]), "+f"(e[95]), "+f"(e[96]), "+f"(e[97]), "+f"(e[98]), "+f"(e[99]), "+f"(e[100]),
      "+f"(e[101]), "+f"(e[102]), "+f"(e[103]), "+f"(e[104]), "+f"(e[105]), "+f"(e[106]), "+f"(e[107]), "+f"(e[108]), "+f"(e[109]), "+f"(e[110]),
      "+f"(e[111]), "+f"(e[112]), "+f"(e[113]), "+f"(e[114]), "+f"(e[115]), "+f"(e[116]), "+f"(e[117]), "+f"(e[118]), "+f"(e[119]), "+f"(e[120]),
      "+f"(e[121]), "+f"(e[122]), "+f"(e[123]), "+f"(e[124]), "+f"(e[125]), "+f"(e[126]), "+f"(e[127])
    : "r"(a[56]), "r"(a[57]), "r"(a[58]), "r"(a[59]), "r"(a[60]), "r"(a[61]), "r"(a[62]), "r"(a[63]), "l"(db));
}

namespace {

constexpr int S_ = 2048, D_ = 512, F_ = 1792;
constexpr int SLOT = 16384;
constexpr int OFF_X = 96 * 1024;
constexpr int OFF_EXCH = 160 * 1024;
constexpr int OFF_HST = 192 * 1024;
constexpr int OFF_BAR = 224 * 1024;
constexpr int SMEM_BYTES = OFF_BAR + 512 + 1024;
constexpr int REC_BYTES = 4128;
constexpr int CV_O = REC_BYTES;
constexpr int CV_E = CV_O + 259 * 16;
constexpr int CV_RAW = CV_E + 16;
constexpr int CV_TX = REC_BYTES + 4096;
constexpr int OFF_PK = 160 * 1024, OFF_PV = 208 * 1024;
constexpr int SPIN_LIMIT = 1 << 22;
constexpr int LAGKB = 6;
constexpr int XL = 4;
constexpr int NW0 = 6;
constexpr int NPOLL = 4, POLLGAP = 80;
constexpr int XQ = 8;

constexpr int BAR_FULL = 0, BAR_EMPTY = 12, BAR_X = 24, BAR_HF = 32, BAR_READY = 40, BAR_KV = 44, BAR_Z = 45, BAR_CV = 47, BAR_XT = 55, BAR_XF = 57, BAR_HE = 59, BAR_KV2 = 60, BAR_U3 = 63;

}

__device__ __align__(1024) __nv_bfloat16 g_h[S_ * F_];
__device__ __align__(1024) __nv_bfloat16 g_zT[D_ * S_];
__device__ __align__(1024) uint4 g_rec[D_ * (REC_BYTES / 16)];
__device__ __align__(128) unsigned g_hflag[16 * 28 * 8];
__device__ __align__(128) unsigned g_kvflag[4 * 32];
__device__ __align__(128) unsigned g_zflag[4 * 32];
__device__ unsigned g_done;
__device__ unsigned g_epoch;

namespace {

__device__ __forceinline__ void wg_fence() { asm volatile("wgmma.fence.sync.aligned;" ::: "memory"); }
__device__ __forceinline__ void wg_commit() { asm volatile("wgmma.commit_group.sync.aligned;" ::: "memory"); }
template <int N> __device__ __forceinline__ void wg_wait() { asm volatile("wgmma.wait_group.sync.aligned %0;" ::"n"(N) : "memory"); }
template <int N = 64>
__device__ __forceinline__ void acc_fence(float* d) {
#pragma unroll
  for (int i = 0; i < N; i++) asm volatile("" : "+f"(d[i])::"memory");
}
__device__ __forceinline__ uint64_t mkdesc(uint32_t addr, uint32_t lbo, uint32_t sbo, uint32_t mode) {
  uint32_t lo = ((addr & 0x3FFFF) >> 4) | ((lbo >> 4) << 16);
  uint32_t hi = (sbo >> 4) | (mode << 30);
  return ((uint64_t)hi << 32) | lo;
}
__device__ __forceinline__ uint64_t desc_of(uint32_t lo, uint32_t hi) { return ((uint64_t)hi << 32) | lo; }
constexpr uint32_t DHI_SW128 = (1024 >> 4) | (1u << 30);
__device__ __forceinline__ void mbar_init(uint32_t bar, uint32_t cnt) { asm volatile("mbarrier.init.shared::cta.b64 [%0], %1;" ::"r"(bar), "r"(cnt) : "memory"); }
__device__ __forceinline__ void mbar_expect_tx(uint32_t bar, uint32_t bytes) { asm volatile("mbarrier.arrive.expect_tx.shared::cta.b64 _, [%0], %1;" ::"r"(bar), "r"(bytes) : "memory"); }
__device__ __forceinline__ void mbar_arrive(uint32_t bar) { asm volatile("mbarrier.arrive.shared::cta.b64 _, [%0];" ::"r"(bar) : "memory"); }
__device__ __forceinline__ void mbar_arrive_n(uint32_t bar, uint32_t n) { asm volatile("mbarrier.arrive.shared::cta.b64 _, [%0], %1;" ::"r"(bar), "r"(n) : "memory"); }
__device__ __forceinline__ void mbar_arrive_remote_n(uint32_t bar, uint32_t cta, uint32_t n) {
  asm volatile("{\n.reg .b32 ra;\nmapa.shared::cluster.u32 ra, %0, %1;\nmbarrier.arrive.shared::cluster.b64 _, [ra], %2;\n}" ::"r"(bar), "r"(cta), "r"(n) : "memory");
}
__device__ __forceinline__ bool mbar_try(uint32_t bar, uint32_t parity) {
  uint32_t ok;
  asm volatile("{\n.reg .pred p;\nmbarrier.try_wait.parity.shared::cta.b64 p, [%1], %2;\nselp.u32 %0, 1, 0, p;\n}" : "=r"(ok) : "r"(bar), "r"(parity) : "memory");
  return ok;
}
__device__ __forceinline__ bool mbar_test(uint32_t bar, uint32_t parity) {
  uint32_t ok;
  asm volatile("{\n.reg .pred p;\nmbarrier.test_wait.parity.shared::cta.b64 p, [%1], %2;\nselp.u32 %0, 1, 0, p;\n}" : "=r"(ok) : "r"(bar), "r"(parity) : "memory");
  return ok;
}
__device__ __forceinline__ void mbar_wait(uint32_t bar, uint32_t parity) {
  if (mbar_try(bar, parity)) return;
#pragma unroll 1
  for (int i = 0; i < SPIN_LIMIT; i++)
    if (mbar_try(bar, parity)) return;
  __trap();
}
__device__ __forceinline__ bool elect_one() {
  uint32_t p;
  asm volatile("{\n.reg .pred P;\nelect.sync _|P, 0xffffffff;\nselp.u32 %0, 1, 0, P;\n}" : "=r"(p));
  return p;
}
__device__ __forceinline__ void tma2d(uint32_t dst, const CUtensorMap* m, int c0, int c1, uint32_t bar) {
  asm volatile("cp.async.bulk.tensor.2d.shared::cluster.global.mbarrier::complete_tx::bytes [%0], [%1, {%3, %4}], [%2];"
               ::"r"(dst), "l"(m), "r"(bar), "r"(c0), "r"(c1) : "memory");
}
__device__ __forceinline__ void tma3d(uint32_t dst, const CUtensorMap* m, int c1, int c2, uint32_t bar) {
  asm volatile("cp.async.bulk.tensor.3d.shared::cluster.global.mbarrier::complete_tx::bytes [%0], [%1, {%3, %4, %5}], [%2];"
               ::"r"(dst), "l"(m), "r"(bar), "r"(0), "r"(c1), "r"(c2) : "memory");
}
__device__ __forceinline__ void tma2d_mc(uint32_t dst, const CUtensorMap* m, int c0, int c1, uint32_t bar) {
  asm volatile("cp.async.bulk.tensor.2d.shared::cluster.global.mbarrier::complete_tx::bytes.multicast::cluster [%0], [%1, {%3, %4}], [%2], %5;"
               ::"r"(dst), "l"(m), "r"(bar), "r"(c0), "r"(c1), "h"((uint16_t)3) : "memory");
}
__device__ __forceinline__ void tma2d_store(const CUtensorMap* m, uint32_t src, int c0, int c1) {
  asm volatile("cp.async.bulk.tensor.2d.global.shared::cta.bulk_group [%0, {%2, %3}], [%1];" ::"l"(m), "r"(src), "r"(c0), "r"(c1) : "memory");
}
__device__ __forceinline__ void bulk_load(uint32_t dst, const void* src, uint32_t bytes, uint32_t bar) {
  asm volatile("cp.async.bulk.shared::cluster.global.mbarrier::complete_tx::bytes [%0], [%1], %2, [%3];" ::"r"(dst), "l"(src), "r"(bytes), "r"(bar) : "memory");
}
__device__ __forceinline__ void bulk_commit() { asm volatile("cp.async.bulk.commit_group;" ::: "memory"); }
__device__ __forceinline__ void bulk_wait_all() { asm volatile("cp.async.bulk.wait_group 0;" ::: "memory"); }
__device__ __forceinline__ void cp_async_wait(int n) {
  switch (n) {
    case 0: asm volatile("cp.async.wait_group 0;" ::: "memory"); break;
    case 1: asm volatile("cp.async.wait_group 1;" ::: "memory"); break;
    case 2: asm volatile("cp.async.wait_group 2;" ::: "memory"); break;
    case 3: asm volatile("cp.async.wait_group 3;" ::: "memory"); break;
    case 4: asm volatile("cp.async.wait_group 4;" ::: "memory"); break;
    case 5: asm volatile("cp.async.wait_group 5;" ::: "memory"); break;
    case 6: asm volatile("cp.async.wait_group 6;" ::: "memory"); break;
    default: asm volatile("cp.async.wait_group 7;" ::: "memory"); break;
  }
}
__device__ __forceinline__ void fence_async_smem() { asm volatile("fence.proxy.async.shared::cta;" ::: "memory"); }
__device__ __forceinline__ void fence_async_global() { asm volatile("fence.proxy.async.global;" ::: "memory"); }
__device__ __forceinline__ void red_release(unsigned* p, unsigned n) { asm volatile("red.release.gpu.global.add.u32 [%0], %1;" ::"l"(p), "r"(n) : "memory"); }
__device__ __forceinline__ void flag_wait(const unsigned* p, unsigned target) {
#pragma unroll 1
  for (int i = 0; i < SPIN_LIMIT; i++) {
    unsigned v;
    asm volatile("ld.acquire.gpu.global.u32 %0, [%1];" : "=r"(v) : "l"(p) : "memory");
    if ((int)(v - target) >= 0) return;
  }
  __trap();
}
__device__ __forceinline__ void flag_wait_fast(const unsigned* p, unsigned target) {
  unsigned v[NPOLL];
#pragma unroll
  for (int j = 0; j < NPOLL; j++) {
    asm volatile("ld.relaxed.gpu.global.u32 %0, [%1];" : "=r"(v[j]) : "l"(p) : "memory");
    __nanosleep(POLLGAP);
  }
#pragma unroll 1
  for (int i = 0; i < SPIN_LIMIT; i++) {
#pragma unroll
    for (int j = 0; j < NPOLL; j++) {
      if ((int)(v[j] - target) >= 0) {
        asm volatile("fence.acquire.gpu;" ::: "memory");
        return;
      }
      asm volatile("ld.relaxed.gpu.global.u32 %0, [%1];" : "=r"(v[j]) : "l"(p) : "memory");
    }
  }
  __trap();
}
__device__ __forceinline__ void ldsm4(uint32_t* r, uint32_t a) {
  asm volatile("ldmatrix.sync.aligned.m8n8.x4.shared.b16 {%0,%1,%2,%3}, [%4];" : "=r"(r[0]), "=r"(r[1]), "=r"(r[2]), "=r"(r[3]) : "r"(a) : "memory");
}
__device__ __forceinline__ void ldsm4t(uint32_t* r, uint32_t a) {
  asm volatile("ldmatrix.sync.aligned.m8n8.x4.trans.shared.b16 {%0,%1,%2,%3}, [%4];" : "=r"(r[0]), "=r"(r[1]), "=r"(r[2]), "=r"(r[3]) : "r"(a) : "memory");
}
__device__ __forceinline__ void stsm4(uint32_t a, uint32_t r0, uint32_t r1, uint32_t r2, uint32_t r3) {
  asm volatile("stmatrix.sync.aligned.m8n8.x4.shared.b16 [%0], {%1,%2,%3,%4};" ::"r"(a), "r"(r0), "r"(r1), "r"(r2), "r"(r3) : "memory");
}
__device__ __forceinline__ void stsm4t(uint32_t a, uint32_t r0, uint32_t r1, uint32_t r2, uint32_t r3) {
  asm volatile("stmatrix.sync.aligned.m8n8.x4.trans.shared.b16 [%0], {%1,%2,%3,%4};" ::"r"(a), "r"(r0), "r"(r1), "r"(r2), "r"(r3) : "memory");
}
__device__ __forceinline__ uint32_t lds32(uint32_t a) {
  uint32_t v;
  asm volatile("ld.shared.u32 %0, [%1];" : "=r"(v) : "r"(a) : "memory");
  return v;
}
__device__ __forceinline__ void row_stats(float* c, uint32_t x) {
  asm volatile("mma.sync.aligned.m16n8k8.row.col.f32.bf16.bf16.f32 {%0,%1,%2,%3}, {%4,%5}, {%4}, {%0,%1,%2,%3};"
               : "+f"(c[0]), "+f"(c[1]), "+f"(c[2]), "+f"(c[3]) : "r"(x), "r"(0x3F803F80u));
}
__device__ __forceinline__ uint32_t pack_bf16(float lo, float hi) {
  uint32_t r;
  asm("cvt.rn.bf16x2.f32 %0, %1, %2;" : "=r"(r) : "f"(hi), "f"(lo));
  return r;
}
__device__ __forceinline__ float bf_lo(uint32_t v) { return __uint_as_float(v << 16); }
__device__ __forceinline__ float bf_hi(uint32_t v) { return __uint_as_float(v & 0xffff0000u); }
__device__ __forceinline__ float bf_round(float x) { return bf_lo(pack_bf16(x, 0.f)); }
__device__ __forceinline__ uint32_t hadd2(uint32_t a, uint32_t b) { uint32_t r; asm("add.rn.bf16x2 %0, %1, %2;" : "=r"(r) : "r"(a), "r"(b)); return r; }
__device__ __forceinline__ uint32_t hsub2(uint32_t a, uint32_t b) { uint32_t r; asm("sub.rn.bf16x2 %0, %1, %2;" : "=r"(r) : "r"(a), "r"(b)); return r; }
__device__ __forceinline__ uint32_t hfma2(uint32_t a, uint32_t b, uint32_t c) { uint32_t r; asm("fma.rn.bf16x2 %0, %1, %2, %3;" : "=r"(r) : "r"(a), "r"(b), "r"(c)); return r; }
__device__ __forceinline__ uint32_t hmul2(uint32_t a, uint32_t b) { uint32_t r; asm("mul.rn.bf16x2 %0, %1, %2;" : "=r"(r) : "r"(a), "r"(b)); return r; }
__device__ __forceinline__ float sqrt_fast(float x) { float r; asm("sqrt.approx.f32 %0, %1;" : "=f"(r) : "f"(x)); return r; }
__device__ __forceinline__ float rcp_fast(float x) { float r; asm("rcp.approx.f32 %0, %1;" : "=f"(r) : "f"(x)); return r; }
__device__ __forceinline__ void bar_sync(int id, int n) { asm volatile("bar.sync %0, %1;" ::"r"(id), "r"(n) : "memory"); }
__device__ __forceinline__ void bar_arrive(int id, int n) { asm volatile("bar.arrive %0, %1;" ::"r"(id), "r"(n) : "memory"); }

__device__ __forceinline__ void cluster_arrive() { asm volatile("barrier.cluster.arrive.relaxed.aligned;" ::: "memory"); }
__device__ __forceinline__ void cluster_wait() { asm volatile("barrier.cluster.wait.aligned;" ::: "memory"); }

struct RowC { float k0, k1; };
template <int N>
__device__ __forceinline__ void geglu(float* g, float* u, const RowC& r0, const RowC& r1, uint32_t zero) {
  float link = 0.f;
#pragma unroll
  for (int i = 0; i < N; i++) {
    const RowC& r = (i & 2) ? r1 : r0;
    const float w = fmaf(fmaf(g[i], g[i], link), r.k1, r.k0), p = fmaf(u[i], g[i], link);
    float th;
    asm("tanh.approx.f32 %0, %1;" : "=f"(th) : "f"(g[i] * w));
    u[i] = fmaf(p, th, p);
    link = __uint_as_float(__float_as_uint(w) & zero);
  }
}

__device__ __forceinline__ void conv_frag(uint32_t* a, uint32_t base) {
  a[0] = lds32(base);
  a[1] = lds32(base + 128);
  a[2] = lds32(base + 16);
  a[3] = lds32(base + 144);
}
__device__ __forceinline__ constexpr int conv_step(int p) { return p == 0 ? 0 : 16 - p; }

__device__ __forceinline__ int unit_of(int u, int rk) { return u < 3 ? 8 * u + rk : 24 + (rk & 3); }
__device__ __forceinline__ int conv_slot(int c) { return (c + 4) & 7; }

__device__ __forceinline__ int next_pair(int p) { return p == 10 ? 2 : p == 8 ? 0 : p == 0 ? 10 : p + 2; }

template <int V> struct IC { static constexpr int value = V; };

struct Maps {
  CUtensorMap x, wg, wu, pk, pv, w2, h, xe, z, o;
};

}

template <int KB, int I>
__device__ __forceinline__ void x_cp(uint32_t d0, uint32_t d1, const void* src) {
  asm volatile("cp.async.cg.shared.global [%0 + %2], [%1 + %3], 16;" ::"r"((I & 1) ? d1 : d0), "l"(src), "n"(OFF_X + KB * SLOT + I * 512), "n"(I * 4096 + KB * 128) : "memory");
  if constexpr (I == 3) asm volatile("cp.async.commit_group;" ::: "memory");
  if constexpr (I < 3) x_cp<KB, I + 1>(d0, d1, src);
  else if constexpr (KB + 1 < XL) x_cp<KB + 1, 0>(d0, d1, src);
}

__global__ void __cluster_dims__(2, 1, 1) __launch_bounds__(384, 1)
fused_kernel(const __nv_bfloat16* __restrict__ gx, __nv_bfloat16* __restrict__ gout, const __nv_bfloat16* __restrict__ gshift,
             const __nv_bfloat16* __restrict__ gssm, const __nv_bfloat16* __restrict__ gD, uint32_t zero, const __grid_constant__ Maps maps) {
  extern __shared__ uint8_t smem_raw[];
  const uint32_t sb = ((uint32_t)__cvta_generic_to_shared(smem_raw) + 1023) & ~1023u;
  if (threadIdx.x < 256) {
    const uint32_t tid = threadIdx.x, row = (tid >> 5) * 16 + ((tid >> 3) & 3), ch = tid & 7;
    const uint32_t d0 = sb + row * 128 + ((ch ^ (row & 3)) << 4);
    x_cp<0, 0>(d0, d0 ^ 64, (const uint8_t*)gx + ((blockIdx.x & 60) * 32768 + row * 1024 + ch * 16));
  }
  const uint32_t bars = sb + OFF_BAR;
  const int warp = __shfl_sync(0xffffffff, threadIdx.x >> 5, 0);
  const int lane = threadIdx.x & 31;
  const int bid = blockIdx.x;
  const int mt = (bid & 63) >> 2, rk = (bid & 3) + (bid < 64 ? 4 : 0);
  const uint32_t rank = bid & 1;
  const bool typeA = rk < 4;

  if (warp >= 8) asm volatile("setmaxnreg.dec.sync.aligned.u32 40;");
  if (elect_one()) {
    mbar_init(bars + 8 * (warp < 8 ? BAR_FULL + warp : BAR_X + 4 + warp - 8), 1);
    asm volatile("fence.mbarrier_init.release.cluster;" ::: "memory");
  }
  __syncwarp();
  cluster_arrive();
  if (warp == 8) {
    cluster_wait();
    cluster_arrive();
    if (elect_one()) {
      fence_async_smem();
#pragma unroll
      for (int kb = 4; kb < 8; kb++) mbar_expect_tx(bars + 8 * (BAR_X + kb), SLOT);
#pragma unroll
      for (int i = 2; i < 4; i++) {
        int kb = 2 * i + rank;
        tma2d_mc(sb + OFF_X + kb * SLOT, &maps.x, kb * 64, mt * 128, bars + 8 * (BAR_X + kb));
      }
#pragma unroll
      for (int kb = 0; kb < NW0; kb++) {
        const uint32_t fb = bars + 8 * (BAR_FULL + kb), dst = sb + kb * SLOT;
        mbar_expect_tx(fb, SLOT);
        tma2d(dst, &maps.wg, rk * 64, kb * 64, fb);
        tma2d(dst + 8192, &maps.wu, rk * 64, kb * 64, fb);
      }
    }
    __syncwarp();
    cluster_wait();
  } else {
    const int wi = warp < 8 ? warp : warp - 1;
    if (elect_one()) {
#pragma unroll
      for (int i = 0; i < 5; i++) {
        const int j = wi * 5 + i, b = j + (j < 20 ? 8 : 12);
        if (b < 64) {
          mbar_init(bars + 8 * b, b < BAR_EMPTY ? 1 : b < BAR_X ? ((typeA && !(b & 1)) ? 16 : 8) : (b >= BAR_HF && b < BAR_READY) || b == BAR_XF || b == BAR_XF + 1 ? 4 : 1);
          if (b >= BAR_X && b < BAR_X + 4) mbar_arrive(bars + 8 * b);
        }
      }
      asm volatile("fence.mbarrier_init.release.cluster;" ::: "memory");
    }
    __syncwarp();
    cluster_wait();
    cluster_arrive();
    __syncwarp();
    cluster_wait();
  }

  if (warp >= 8) {
    auto load_conv = [&](int c, uint32_t par) {
      const int cs = conv_slot(c), ch = (mt * 4 + rk - 4) * 8 + c;
      mbar_wait(bars + 8 * (BAR_EMPTY + cs), par);
      if (elect_one()) {
        const uint32_t fb = bars + 8 * (BAR_X + c), dst = sb + cs * SLOT;
        mbar_expect_tx(fb, CV_TX);
        bulk_load(dst, (const uint8_t*)g_rec + (size_t)ch * REC_BYTES, REC_BYTES, fb);
        bulk_load(dst + CV_RAW, gssm + (size_t)ch * S_, 4096, fb);
      }
      __syncwarp();
    };
    if (warp == 8) {
      int slot = NW0;
      uint32_t emask = 0x3F >> NW0 << NW0;
      auto load_q = [&](int q, int p) {
        mbar_wait(bars + 8 * (BAR_EMPTY + p + 1), (emask >> (p + 1)) & 1);
        if (elect_one()) {
          const uint32_t fb = bars + 8 * (BAR_FULL + p + 1);
          mbar_expect_tx(fb, SLOT);
          tma3d(sb + (p + 1) * SLOT, &maps.w2, q * 64, rk * 2, fb);
        }
        __syncwarp();
        if ((q & 7) == 0) mbar_wait(bars + 8 * (BAR_READY + (q >> 3)), 0);
        mbar_wait(bars + 8 * (BAR_EMPTY + p), (emask >> p) & 1);
        emask ^= 3u << p;
        if (elect_one()) {
          const uint32_t fb = bars + 8 * (BAR_FULL + p);
          mbar_expect_tx(fb, SLOT);
          tma2d_mc(sb + p * SLOT + rank * 8192, &maps.h, q * 64, mt * 128 + rank * 64, fb);
        }
        __syncwarp();
      };
      for (int u = 0; u < 4; u++) {
        const int f0 = unit_of(u, rk) * 64;
        if (u == 3) {
          if (lane == 0) mbar_arrive(bars + 8 * BAR_U3);
          if (typeA) break;
        }
#pragma unroll 1
        for (int kb = u == 0 ? NW0 : 0; kb < 8; kb++) {
          if (u == 3 && !typeA && slot == 4) slot = 8;
          mbar_wait(bars + 8 * (BAR_EMPTY + slot), (emask >> slot) & 1);
          emask ^= 1u << slot;
          if (elect_one()) {
            const uint32_t fb = bars + 8 * (BAR_FULL + slot), dst = sb + slot * SLOT;
            mbar_expect_tx(fb, SLOT);
            tma2d(dst, &maps.wg, f0, kb * 64, fb);
            tma2d(dst + 8192, &maps.wu, f0, kb * 64, fb);
            const int pc = 8 * u + kb - 7;
            if (pc >= 0 && pc < 4) {
              const int r0 = (bid >> 2) * 64 + 16 * pc;
              const uint32_t kb_ = bars + 8 * (pc == 0 ? BAR_KV : BAR_KV2 + pc - 1);
              mbar_expect_tx(kb_, pc == 0 ? 3 * 4096 : 2 * 4096);
              if (pc == 0) tma2d(sb + OFF_PK, &maps.pk, (bid & 3) * 128, r0 - 16, kb_);
              tma2d(sb + OFF_PK + 4096 * (pc + 1), &maps.pk, (bid & 3) * 128, r0, kb_);
              tma2d(sb + OFF_PV + 4096 * pc, &maps.pv, (bid & 3) * 128, r0, kb_);
            }
          }
          __syncwarp();
          if (++slot == 10) slot = 0;
        }
      }
      if (typeA) {
        int p = 10;
        emask ^= 0x3F3;
#pragma unroll 1
        for (int q = 0; q < 28; q++) {
          if (q >= 2 && q < 6) {
            mbar_wait(bars + 8 * (BAR_X + 2 * q - 4), 1);
            mbar_wait(bars + 8 * (BAR_X + 2 * q - 3), 1);
          }
          load_q(q, p);
          p = next_pair(p);
        }
      } else {
        mbar_wait(bars + 8 * BAR_READY, 0);
#pragma unroll 1
        for (int c = 4; c < 8; c++) load_conv(c, (emask >> (c - 4)) & 1);
      }
    } else if (warp == 9) {
      if (lane >= 3 && lane < 10) asm volatile("prefetch.tensormap [%0];" ::"l"(&maps.x + lane) : "memory");
      if (lane == 0) {
#pragma unroll 1
        for (int u = 0; u < 4; u++) {
#pragma unroll
          for (int i = 0; i < 2; i++) {
            if (u < 3 || typeA == (i == 0)) {
              mbar_wait(bars + 8 * (BAR_HF + 2 * u + i), 0);
              tma2d_store(&maps.h, sb + OFF_HST + i * 8192, unit_of(u, rk) * 64, mt * 128 + 64 * i);
              bulk_commit();
            }
          }
          bulk_wait_all();
          mbar_arrive(bars + 8 * BAR_HE);
          if (u == 3 && typeA) {
#pragma unroll
            for (int i = 0; i < 2; i++) {
              mbar_expect_tx(bars + 8 * (BAR_XT + i), SLOT);
              tma2d(sb + OFF_HST + i * SLOT, &maps.xe, rk * 128, mt * 128 + 64 * i, bars + 8 * (BAR_XT + i));
              tma2d(sb + OFF_HST + i * SLOT + 8192, &maps.xe, rk * 128 + 64, mt * 128 + 64 * i, bars + 8 * (BAR_XT + i));
            }
          }
          red_release(&g_hflag[(mt * 28 + unit_of(u, rk)) * 8], u < 3 ? 2 : 1);
        }
      }
      __syncwarp();
    } else {
      {
        const int mem = lane & 1;
        uint4 cf[2];
#pragma unroll
        for (int ps = 0; ps < 2; ps++) cf[ps] = __ldg((const uint4*)(gshift + ((bid & 3) * 128 + 2 * ((2 * ps + warp - 10) * 16 + (lane >> 1))) * 4));
        uint8_t* rec = (uint8_t*)g_rec + (size_t)((bid & 3) * 128 + 2 * ((warp - 10) * 16 + (lane >> 1))) * REC_BYTES + mem * 16;
        if (bid < 4) {
#pragma unroll
          for (int i = 0; i < 4; i++) *(uint4*)(rec + ((i >> 1) * 64 + (i & 1)) * REC_BYTES + 4096) = make_uint4(0, 0, 0, 0);
        }
        rec += 2 * (2032 - (bid >> 2) * 64);
        uint32_t pk = sb + OFF_PK + 13 * 256 + (mem ? 0 : 2048) + ((warp - 10) * 16 + (lane >> 1)) * 4;
#pragma unroll 1
        for (int tk = 0; tk < 4; tk++) {
          mbar_wait(bars + 8 * (tk == 0 ? BAR_KV : BAR_KV2 + tk - 1), 0);
#pragma unroll
          for (int ps = 0; ps < 2; ps++) {
            const uint32_t x0 = __byte_perm(cf[ps].x, cf[ps].z, 0x5410), x1 = __byte_perm(cf[ps].x, cf[ps].z, 0x7632);
            const uint32_t x2 = __byte_perm(cf[ps].y, cf[ps].w, 0x5410), x3 = __byte_perm(cf[ps].y, cf[ps].w, 0x7632);
            uint32_t kn[11], o[8];
#pragma unroll
            for (int r = 0; r < 11; r++) kn[r] = lds32(pk + ps * 128 + r * 256);
#pragma unroll
            for (int r = 0; r < 8; r++) o[r] = lds32(pk + ps * 128 + (OFF_PV - OFF_PK - 13 * 256) + r * 256);
#pragma unroll
            for (int r = 0; r < 8; r++) o[r] = hmul2(hfma2(kn[r + 3], x0, hfma2(kn[r + 2], x1, hfma2(kn[r + 1], x2, hmul2(kn[r], x3)))), o[r]);
            uint8_t* p = rec + ps * 64 * REC_BYTES;
            *(uint4*)p = make_uint4(__byte_perm(o[7], o[6], 0x5410), __byte_perm(o[5], o[4], 0x5410), __byte_perm(o[3], o[2], 0x5410), __byte_perm(o[1], o[0], 0x5410));
            *(uint4*)(p + REC_BYTES) = make_uint4(__byte_perm(o[7], o[6], 0x7632), __byte_perm(o[5], o[4], 0x7632), __byte_perm(o[3], o[2], 0x7632), __byte_perm(o[1], o[0], 0x7632));
          }
          pk += 4096;
          rec -= 32;
        }
        __syncwarp();
        if (typeA && lane == 0) {
          mbar_arrive_n(bars + 8 * (BAR_EMPTY + 10), 4);
          mbar_arrive_n(bars + 8 * (BAR_EMPTY + 11), 4);
          mbar_arrive_remote_n(bars + 8 * (BAR_EMPTY + 10), rank ^ 1, 4);
        }
      }
      if (warp == 10) {
        bar_arrive(8, 64);
      } else {
        bar_sync(8, 64);
        if (lane == 0) red_release(&g_kvflag[(bid & 3) * 32], 1);
      }
      unsigned epoch;
      asm volatile("ld.relaxed.gpu.global.u32 %0, [%1];" : "=r"(epoch) : "l"(&g_epoch) : "memory");
      if (warp == 10) {
        if (typeA) {
#pragma unroll 1
          for (int grp = 0; grp < 4; grp++) {
            const int q = 8 * grp + (lane & (grp < 3 ? 7 : 3));
            flag_wait(&g_hflag[(mt * 28 + q) * 8], 2 * (epoch + 1));
            __syncwarp();
            fence_async_global();
            __syncwarp();
            if (lane == 0) mbar_arrive(bars + 8 * (BAR_READY + grp));
          }
        } else {
          flag_wait(&g_kvflag[(mt >> 2) * 32], 32 * (epoch + 1));
          fence_async_global();
          if (lane == 0) mbar_arrive(bars + 8 * BAR_READY);
          mbar_wait(bars + 8 * BAR_U3, 0);
          load_conv(0, 1);
          load_conv(1, 1);
        }
      }
      if (typeA && warp == 11) {
        mbar_wait(bars + 8 * BAR_U3, 0);
#pragma unroll 1
        for (int kb = 0; kb < 8; kb++) {
          const int sl = kb < 6 ? 4 + kb : kb - 6;
          mbar_wait(bars + 8 * (BAR_EMPTY + sl), kb < 2);
          if (elect_one()) {
            const uint32_t fb = bars + 8 * (BAR_X + kb), dst = sb + sl * SLOT;
            mbar_expect_tx(fb, SLOT);
            tma2d(dst, &maps.wg, (24 + rk) * 64, kb * 64, fb);
            tma2d(dst + 8192, &maps.wu, (24 + rk) * 64, kb * 64, fb);
          }
          __syncwarp();
        }
      }
      if (typeA) {
        mbar_wait(bars + 8 * (BAR_XF + warp - 10), 0);
        if (lane == 0) mbar_expect_tx(bars + 8 * (BAR_Z + warp - 10), SLOT);
        flag_wait_fast(&g_zflag[rk * 32], 128 * (epoch + 1));
        fence_async_global();
        if (elect_one()) {
          tma2d(sb + OFF_HST + (warp - 10) * SLOT, &maps.z, mt * 128 + (warp - 10) * 64, rk * 128, bars + 8 * (BAR_Z + warp - 10));
        }
        __syncwarp();
      }
      if (lane == 0) {
        unsigned old = atomicAdd(&g_done, 1u);
        if (old == 2 * gridDim.x - 1) {
          g_done = 0;
          g_epoch = epoch + 1;
        }
      }
      if (!typeA) {
        const uint4 dv = __ldg((const uint4*)(gD + (mt * 4 + rk - 4) * 8));
#pragma unroll 1
        for (int cc = 0; cc < 4; cc++) {
          const int c = 2 * cc + (warp - 10);
          const uint32_t dw = cc == 0 ? dv.x : cc == 1 ? dv.y : cc == 2 ? dv.z : dv.w;
          const uint32_t sl = sb + conv_slot(c) * SLOT;
          mbar_wait(bars + 8 * (BAR_X + c), 1);
          if (lane == 0) {
            const uint32_t k01 = hadd2(lds32(sl + CV_RAW), warp == 10 ? (dw & 0xffffu) : (dw >> 16));
            asm volatile("st.shared.u32 [%0], %1;" ::"r"(sl + CV_RAW), "r"(k01) : "memory");
            asm volatile("st.shared.v4.u32 [%0], {%1,%1,%1,%1};" ::"r"(sl + CV_E), "r"(0) : "memory");
            asm volatile("st.shared.u32 [%0], %1;" ::"r"(sl + CV_RAW + 4096), "r"(0) : "memory");
          }
          __syncwarp();
          const uint32_t p = sl + lane * 16;
#pragma unroll
          for (int i0 = 0; i0 < 9; i0 += 3) {
            uint32_t a[3][5];
#pragma unroll
            for (int i = 0; i < 3; i++) {
              if (i0 + i < 8 || lane == 0) {
                asm volatile("ld.shared.v4.u32 {%0,%1,%2,%3}, [%4];" : "=r"(a[i][0]), "=r"(a[i][1]), "=r"(a[i][2]), "=r"(a[i][3]) : "r"(p + CV_E + (i0 + i) * 512) : "memory");
                a[i][4] = lds32(p + CV_RAW + (i0 + i) * 512);
              }
            }
#pragma unroll
            for (int i = 0; i < 3; i++) {
              if (i0 + i < 8 || lane == 0)
                asm volatile("st.shared.v4.u32 [%0], {%1,%2,%3,%4};" ::"r"(p + CV_O + (i0 + i) * 512), "r"(__byte_perm(a[i][0], a[i][1], 0x5432)),
                             "r"(__byte_perm(a[i][1], a[i][2], 0x5432)), "r"(__byte_perm(a[i][2], a[i][3], 0x5432)), "r"(__byte_perm(a[i][3], a[i][4], 0x5432)) : "memory");
            }
          }
          __syncwarp();
          if (lane == 0) mbar_arrive(bars + 8 * (BAR_CV + c));
          if (c == 0) {
            load_conv(2, 0);
            load_conv(3, 0);
          }
        }
      }
    }
    __syncwarp();
  } else {
    asm volatile("setmaxnreg.inc.sync.aligned.u32 232;");
    const int wg = warp >> 2, w = warp & 3;
    const int g = lane >> 2, t = lane & 3;
    const uint32_t peer = rank ^ 1;
    const int lrow = 16 * w + ((lane >> 3) & 1) * 8 + (lane & 7);
    const int lch = lane >> 4;
    float d[64];
    uint32_t mm;
    int slot = 0;
    uint32_t fmask = 0;
    auto release = [&](int s, int n = 1) {
      asm volatile("{\n.reg .pred p, q;\n.reg .b32 ra;\nsetp.eq.u32 p, %1, 0;\nsetp.eq.and.u32 q, %2, 0, p;\n"
                   "mapa.shared::cluster.u32 ra, %0, %3;\n@p mbarrier.arrive.shared::cta.b64 _, [%0], %4;\n@q mbarrier.arrive.shared::cluster.b64 _, [ra], %4;\n}"
                   ::"r"(bars + 8 * (BAR_EMPTY + s)), "r"(lane), "r"((s & 1) | (rk & 4)), "r"(peer), "r"(n) : "memory");
    };
    const uint32_t dw0 = ((sb & 0x3FFFF) >> 4) | ((8192 >> 4) << 16);
    const int nu = (typeA == (wg == 0)) ? 4 : 3;
    RowC rc0, rc1;
    auto epilogue = [&](int u) {
      geglu<32>(d, d + 32, rc0, rc1, zero);
      const uint32_t hrow = sb + OFF_HST + wg * 8192 + lrow * 128;
#pragma unroll
      for (int i = 0; i < 8; i += 2) {
        const float* h = d + 32 + 4 * i;
        stsm4(hrow + (((i + lch) ^ (lane & 7)) << 4), pack_bf16(h[0], h[1]), pack_bf16(h[2], h[3]), pack_bf16(h[4], h[5]), pack_bf16(h[6], h[7]));
      }
      fence_async_smem();
      __syncwarp();
      if (lane == 0) mbar_arrive(bars + 8 * (BAR_HF + 2 * u + wg));
    };
    {
      uint32_t xa[32][4];
      auto center = [&](int kb) {
        const uint32_t m0 = __byte_perm(mm, 0, 0x1010), m1 = __byte_perm(mm, 0, 0x3232);
#pragma unroll
        for (int i = 4 * kb; i < 4 * kb + 4; i++) {
          xa[i][0] = hsub2(xa[i][0], m0);
          xa[i][1] = hsub2(xa[i][1], m1);
          xa[i][2] = hsub2(xa[i][2], m0);
          xa[i][3] = hsub2(xa[i][3], m1);
        }
      };
      const uint32_t xrow = sb + OFF_X + (64 * wg + lrow) * 128;
      {
        float c1[2][4] = {}, c2[2][4] = {};
#pragma unroll
        for (int kb = 0; kb <= 8; kb++) {
          if (kb < 8) {
            if (kb < XL) {
              cp_async_wait(XL - 1 - kb);
              __syncwarp();
            } else {
              mbar_wait(bars + 8 * (BAR_X + kb), 0);
            }
#pragma unroll
            for (int kk = 0; kk < 4; kk++) ldsm4(xa[4 * kb + kk], xrow + kb * SLOT + (((2 * kk + lch) ^ (lane & 7)) << 4));
          }
          if (kb > 0) {
#pragma unroll
            for (int kk = 0; kk < 4; kk++) {
              const uint32_t* a = xa[4 * (kb - 1) + kk];
              row_stats(c1[0], a[0]);
              row_stats(c2[0], a[1]);
              row_stats(c1[1], a[2]);
              row_stats(c2[1], a[3]);
            }
          }
        }
        const int src = (lane & ~3) | (g >> 1);
        const float mean0 = __shfl_sync(0xffffffff, (g & 1) ? c1[0][3] + c1[1][3] : c1[0][2] + c1[1][2], src) * (1.f / 512);
        const float mean1 = __shfl_sync(0xffffffff, (g & 1) ? c2[0][3] + c2[1][3] : c2[0][2] + c2[1][2], src) * (1.f / 512);
        mm = pack_bf16(mean0, mean1);
        if (wg == 1) {
          for (int s = 6; s < 10; s++) release(s);
        }
        center(0);
        rc0.k0 = (g & 1) ? c1[0][1] + c1[1][1] : c1[0][0] + c1[1][0];
        rc1.k0 = (g & 1) ? c2[0][1] + c2[1][1] : c2[0][0] + c2[1][0];
        rc0.k1 = mean0;
        rc1.k1 = mean1;
      }
      bool rdy = false, turn = wg == 1;
      uint32_t nbar = bars + 8 * BAR_FULL, npar = 0;
#pragma unroll 1
      for (int u = 0; u < nu; u++) {
        const int rel = u == 3 ? 2 : 1;
        if (turn) bar_sync(1 + wg, 256);
        if (!rdy) mbar_wait(nbar, npar);
        int s1 = 0;
#pragma unroll
        for (int kb = 0; kb < 8; kb++) {
          const uint64_t db = desc_of(dw0 + slot * 1024, DHI_SW128);
          const uint32_t(*a)[4] = xa + 4 * kb;
          wg_fence();
          if (kb == 0) wgmma_rs_init_n128<1>(d, a[0][0], a[0][1], a[0][2], a[0][3], db);
          else wgmma_rs_n128<1>(d, a[0][0], a[0][1], a[0][2], a[0][3], db, 1);
          int ns = slot == 9 ? 0 : slot + 1;
          if (((kb == 7 && u == 2) || (kb == 5 && u == 3)) && !typeA) ns = 8;
          if (!(typeA && u == 3)) fmask ^= 1u << slot;
          const bool alt = typeA && u == (kb == 7 ? 2 : 3);
          nbar = bars + 8 * (alt ? BAR_X + ((kb + 1) & 7) : BAR_FULL + ns);
          npar = alt ? 1 : (fmask >> ns) & 1;
          rdy = mbar_test(nbar, npar);
          wgmma_rs_n128<1>(d, a[1][0], a[1][1], a[1][2], a[1][3], db + 128, 1);
          wg_commit();
          if (kb >= 1) {
            wg_wait<1>();
            release(s1, rel);
          }
          if (kb == 0 && u == 0 && wg == 0) { release(6); release(7); }
          if (kb == 1 && u == 0 && wg == 0) { release(8); release(9); }
          wgmma_rs_n128<1>(d, a[2][0], a[2][1], a[2][2], a[2][3], db + 256, 1);
          if (kb == LAGKB && u < 3) bar_arrive(2 - wg, 256);
          wgmma_rs_n128<1>(d, a[3][0], a[3][1], a[3][2], a[3][3], db + 384, 1);
          wg_commit();
          if (kb == 7 && wg == 1 && u == 3) bar_arrive(9, 256);
          if (kb < 7 && u == 0) center(kb + 1);
          if (kb < 7 && !rdy) mbar_wait(nbar, npar);
          s1 = slot;
          slot = ns;
        }
        turn = wg == 0 || u < 2;
        if (u == 0) {
          const int src = (lane & ~3) | (g >> 1);
          const float q0 = __shfl_sync(0xffffffff, rc0.k0, src), q1 = __shfl_sync(0xffffffff, rc1.k0, src);
          const float v0 = fmaxf(fmaf(-rc0.k1, rc0.k1, q0 * (1.f / 512)), 0.f), v1 = fmaxf(fmaf(-rc1.k1, rc1.k1, q1 * (1.f / 512)), 0.f);
          const float rs0 = rcp_fast(bf_round(sqrt_fast(bf_round(bf_round(v0) + 1e-5f))));
          const float rs1 = rcp_fast(bf_round(sqrt_fast(bf_round(bf_round(v1) + 1e-5f))));
          rc0 = {0.7978845608028654f * rs0, 0.035677408136300125f * rs0 * rs0 * rs0};
          rc1 = {0.7978845608028654f * rs1, 0.035677408136300125f * rs1 * rs1 * rs1};
        }
        if (u > 0) mbar_wait(bars + 8 * BAR_HE, (u - 1) & 1);
        wg_wait<0>();
        release(s1, rel);
        acc_fence(d);
        epilogue(u);
      }
    }
    if (typeA) {
      uint32_t xr[32], xn[32];
#pragma unroll
      for (int i = 0; i < 64; i++) d[i] = 0.f;
      const float rs0 = rc0.k0 * 1.2533141373155003f, rs1 = rc1.k0 * 1.2533141373155003f;
      int s1 = 0;
      slot = 10;
      mbar_wait(bars + 8 * (BAR_FULL + slot + 1), (fmask >> slot) & 1);
      mbar_wait(bars + 8 * (BAR_FULL + slot), (fmask >> slot) & 1);
      const uint32_t m0 = __byte_perm(mm, 0, 0x1010), m1 = __byte_perm(mm, 0, 0x3232);
      const uint32_t xrow = sb + OFF_HST + wg * SLOT + lrow * 128;
      const uint32_t da0 = (((sb & 0x3FFFF) + wg * 8192) >> 4) | (1 << 16);
      auto step = [&](int q, auto xi) {
        constexpr int XI = decltype(xi)::value;
        const uint64_t da = desc_of(da0 + slot * 1024, DHI_SW128);
        const uint64_t db = desc_of(dw0 + 1024 + slot * 1024, DHI_SW128);
        const int ns = next_pair(slot);
        fmask ^= 3u << slot;
        const uint32_t np = (fmask >> ns) & 1;
        wg_fence();
        wgmma_ss_n128(d, da, db, 1);
        bool rdy = mbar_test(bars + 8 * (BAR_FULL + ns + 1), np);
        wgmma_ss_n128(d, da + 2, db + 128, 1);
        wg_commit();
        if (q >= 1 && q <= 22) {
          wg_wait<1>();
          release(s1);
          release(s1 + 1);
        }
        wgmma_ss_n128(d, da + 4, db + 256, 1);
        rdy = mbar_test(bars + 8 * (BAR_FULL + ns), np) && rdy;
        wgmma_ss_n128(d, da + 6, db + 384, 1);
        wg_commit();
        if constexpr (XI >= 1) {
#pragma unroll
          for (int i = 4 * (XI - 1); i < 4 * XI; i++) {
            const uint32_t dd = hsub2(xr[i], (i & 1) ? m1 : m0);
            const float r = (i & 1) ? rs1 : rs0;
            xn[i] = pack_bf16(bf_lo(dd) * r, bf_hi(dd) * r);
          }
        }
        if constexpr (XI == 0) mbar_wait(bars + 8 * (BAR_XT + wg), 0);
        if constexpr (XI >= 0 && XI < 8) ldsm4(xr + 4 * XI, xrow + (XI >> 2) * 8192 + (((2 * (XI & 3) + lch) ^ (lane & 7)) << 4));
        if constexpr (XI == 8) {
          __syncwarp();
          if (lane == 0) mbar_arrive(bars + 8 * (BAR_XF + wg));
        }
        if (!rdy && q < 27) {
          mbar_wait(bars + 8 * (BAR_FULL + ns + 1), np);
          mbar_wait(bars + 8 * (BAR_FULL + ns), np);
        }
        s1 = slot;
        slot = ns;
      };
#pragma unroll 1
      for (int q = 0; q < XQ; q++) step(q, IC<-1>{});
      step(XQ, IC<0>{}); step(XQ + 1, IC<1>{}); step(XQ + 2, IC<2>{}); step(XQ + 3, IC<3>{}); step(XQ + 4, IC<4>{});
      step(XQ + 5, IC<5>{}); step(XQ + 6, IC<6>{}); step(XQ + 7, IC<7>{}); step(XQ + 8, IC<8>{});
#pragma unroll 1
      for (int q = XQ + 9; q < 28; q++) step(q, IC<-1>{});
      mbar_wait(bars + 8 * (BAR_Z + wg), 0);
      {
        const uint32_t zb = sb + OFF_HST + wg * SLOT + ((lane >> 4) * 8 + (lane & 7)) * 128 + (((2 * w + ((lane >> 3) & 1)) ^ (lane & 7)) << 4);
#pragma unroll
        for (int i = 0; i < 8; i++) {
          uint32_t z[4];
          ldsm4t(z, zb + i * 2048);
#pragma unroll
          for (int e = 0; e < 4; e++) xr[4 * i + e] = hfma2(xn[4 * i + e], z[e], xr[4 * i + e]);
        }
      }
      bar_sync(3 + wg, 128);
      wg_wait<0>();
      acc_fence(d);
      const float h0 = 0.5f * rs0 * rs0, h1 = 0.5f * rs1 * rs1;
      const uint32_t orow = sb + OFF_HST + wg * SLOT + lrow * 128;
#pragma unroll
      for (int i = 0; i < 8; i++) {
        uint32_t r[4];
#pragma unroll
        for (int e = 0; e < 4; e++) r[e] = hadd2(xr[4 * i + e], pack_bf16(d[8 * i + 2 * e] * ((e & 1) ? h1 : h0), d[8 * i + 2 * e + 1] * ((e & 1) ? h1 : h0)));
        stsm4(orow + (i >> 2) * 8192 + (((2 * (i & 3) + lch) ^ (lane & 7)) << 4), r[0], r[1], r[2], r[3]);
        if (i == 3) {
          fence_async_smem();
          __syncwarp();
          if (lane == 0) {
            tma2d_store(&maps.o, sb + OFF_HST + wg * SLOT + w * 2048, rk * 128, mt * 128 + 64 * wg + 16 * w);
            bulk_commit();
          }
        }
      }
      __syncwarp();
      {
        const int r = lane >> 3, ch = lane & 7;
        uint4* op = (uint4*)(gout + (size_t)(mt * 128 + 64 * wg + 16 * w + r) * D_ + rk * 128 + 64) + ch;
#pragma unroll
        for (int i = 0; i < 4; i++) {
          const int row = 4 * i + r;
          uint4 v;
          asm volatile("ld.shared.v4.u32 {%0,%1,%2,%3}, [%4];" : "=r"(v.x), "=r"(v.y), "=r"(v.z), "=r"(v.w)
                       : "r"(sb + OFF_HST + wg * SLOT + 8192 + (16 * w + row) * 128 + ((ch ^ (row & 7)) << 4)) : "memory");
          op[i * 4 * (D_ / 8)] = v;
        }
      }
      if (lane == 0) asm volatile("cp.async.bulk.wait_group.read 0;" ::: "memory");
      __syncwarp();
    } else {
      const int ch0 = (mt * 4 + rk - 4) * 8;
      const int bz = 16 * w + g - 7 + 2 * t;
      const uint32_t aoff = (g & 1) ? CV_E + 2 * (bz + 8) : CV_O + 2 * (bz + 7);
      const uint32_t xb = sb + OFF_EXCH + wg * 16384;
      const uint32_t xw = xb + w * 4096 + (255 + 2 * w - lane) * 16;
      const uint32_t xw0 = lane < 2 * w ? xb + w * 4096 + lane * 16 : xw;
      const int tp = 32 * w + lane;
      float e[128];
      uint32_t a[64];
      mbar_wait(bars + 8 * (BAR_X + 2 * wg), 1);
      mbar_wait(bars + 8 * (BAR_CV + 2 * wg), 0);
#pragma unroll
      for (int j = 0; j < 16; j++) conv_frag(a + 4 * j, sb + conv_slot(2 * wg) * SLOT + aoff + 256 * conv_step(j));
      auto merge = [&](int ch, int k) {
        uint4 v[4];
#pragma unroll
        for (int sw = 0; sw < 4; sw++) {
          v[sw] = make_uint4(0, 0, 0, 0);
          if (k == 1 || sw == 0 || tp >= 2 * sw)
            asm volatile("ld.shared.v4.u32 {%0,%1,%2,%3}, [%4];" : "=r"(v[sw].x), "=r"(v[sw].y), "=r"(v[sw].z), "=r"(v[sw].w) : "r"(xb + sw * 4096 + (128 * k + tp) * 16) : "memory");
        }
        ((uint4*)(g_zT + (size_t)(ch0 + ch) * S_))[128 * k + tp] =
            make_uint4(hadd2(hadd2(v[0].x, v[1].x), hadd2(v[2].x, v[3].x)), hadd2(hadd2(v[0].y, v[1].y), hadd2(v[2].y, v[3].y)),
                       hadd2(hadd2(v[0].z, v[1].z), hadd2(v[2].z, v[3].z)), hadd2(hadd2(v[0].w, v[1].w), hadd2(v[2].w, v[3].w)));
      };
      auto dump = [&](int i) {
        uint32_t r[4];
#pragma unroll
        for (int k = 0; k < 4; k++) {
          const float* p = e + 4 * (4 * i + k);
          r[k] = 4 * i + k < 31 ? pack_bf16(p[0] + p[6], p[1] + p[7]) : pack_bf16(p[0], p[1]);
        }
        stsm4t(i == 0 ? xw0 : xw - 512 * i, r[0], r[1], r[2], r[3]);
      };
      int cp = 0;
      const int ncc = wg ? 3 : 5;
      int c = 2 * wg;
#pragma unroll 1
      for (int cc = 0;; cc++) {
        const bool more = cc + 1 < ncc;
        const int cn = more ? (c == 0 ? 1 : c + 2) : c;
        const uint32_t nbase = sb + conv_slot(cn) * SLOT + aoff;
        bar_sync(c == 1 ? 9 : 1 + wg, 256);
        wg_fence();
        const uint64_t db = mkdesc(sb + conv_slot(c) * SLOT, 16, 128, 0);
        conv_block_0_14(e, a, db);
        wg_commit();
        conv_block_14_16(e, a, db);
        wg_commit();
        wg_wait<1>();
        if (c > 0 && c < 7) bar_arrive(2 - wg, 256);
        mbar_wait(bars + 8 * (BAR_X + cn), 1);
        mbar_wait(bars + 8 * (BAR_CV + cn), 0);
        if (cc > 0) {
          merge(cp, 0);
          merge(cp, 1);
        }
        bar_sync(3 + wg, 128);
        wg_wait<0>();
        acc_fence<128>(e);
        if (!more) break;
#pragma unroll
        for (int i = 0; i < 8; i++) {
#pragma unroll
          for (int j = 2 * i; j < 2 * i + 2; j++) conv_frag(a + 4 * j, nbase + 256 * conv_step(j));
          dump(i);
        }
        cp = c;
        c = cn;
      }
#pragma unroll
      for (int i = 0; i < 8; i++) dump(i);
      bar_sync(3 + wg, 128);
      merge(c, 0);
      merge(c, 1);
      bar_sync(3 + wg, 128);
      if (w == 0 && lane == 0) red_release(&g_zflag[(mt >> 2) * 32], wg ? 3 : 5);
      __syncwarp();
    }
  }
}

namespace {
typedef CUresult (*EncFn)(CUtensorMap*, CUtensorMapDataType, cuuint32_t, void*, const cuuint64_t*, const cuuint64_t*, const cuuint32_t*,
                          const cuuint32_t*, CUtensorMapInterleave, CUtensorMapSwizzle, CUtensorMapL2promotion, CUtensorMapFloatOOBfill);
void make_map(EncFn enc, CUtensorMap* m, const void* base, uint64_t inner, uint64_t outer, uint32_t bi, uint32_t bo, bool swz) {
  cuuint64_t dims[2] = {inner, outer};
  cuuint64_t strides[1] = {inner * 2};
  cuuint32_t box[2] = {bi, bo};
  cuuint32_t es[2] = {1, 1};
  enc(m, CU_TENSOR_MAP_DATA_TYPE_BFLOAT16, 2, const_cast<void*>(base), dims, strides, box, es, CU_TENSOR_MAP_INTERLEAVE_NONE,
      swz ? CU_TENSOR_MAP_SWIZZLE_128B : CU_TENSOR_MAP_SWIZZLE_NONE, CU_TENSOR_MAP_L2_PROMOTION_L2_256B, CU_TENSOR_MAP_FLOAT_OOB_FILL_NONE);
}
}

extern "C" void kernel_launch(void* const* d_in, const int* in_sizes, int n_in, void* d_out, int out_size) {
  (void)in_sizes; (void)n_in; (void)out_size;
  static EncFn enc = nullptr;
  static void *ph = nullptr, *pz = nullptr;
  if (!enc) {
    void* fn = nullptr;
    cudaDriverEntryPointQueryResult st;
    cudaGetDriverEntryPoint("cuTensorMapEncodeTiled", &fn, cudaEnableDefault, &st);
    enc = (EncFn)fn;
    cudaGetSymbolAddress(&ph, g_h);
    cudaGetSymbolAddress(&pz, g_zT);
    cudaFuncSetAttribute(fused_kernel, cudaFuncAttributeMaxDynamicSharedMemorySize, SMEM_BYTES);
  }
  Maps maps;
  make_map(enc, &maps.x, d_in[0], D_, S_, 64, 128, true);
  make_map(enc, &maps.wg, d_in[7], F_, D_, 64, 64, true);
  make_map(enc, &maps.wu, d_in[8], F_, D_, 64, 64, true);
  {
    cuuint64_t dims[3] = {64, F_, 8}, strides[2] = {D_ * 2, 128};
    cuuint32_t box[3] = {64, 64, 2}, es[3] = {1, 1, 1};
    enc(&maps.w2, CU_TENSOR_MAP_DATA_TYPE_BFLOAT16, 3, d_in[9], dims, strides, box, es, CU_TENSOR_MAP_INTERLEAVE_NONE, CU_TENSOR_MAP_SWIZZLE_128B,
        CU_TENSOR_MAP_L2_PROMOTION_L2_256B, CU_TENSOR_MAP_FLOAT_OOB_FILL_NONE);
  }
  make_map(enc, &maps.h, ph, F_, S_, 64, 64, true);
  make_map(enc, &maps.pk, d_in[1], D_, S_, 128, 16, false);
  make_map(enc, &maps.pv, d_in[2], D_, S_, 128, 16, false);
  make_map(enc, &maps.o, d_out, D_, S_, 64, 16, true);
  make_map(enc, &maps.xe, d_in[0], D_, S_, 64, 64, true);
  make_map(enc, &maps.z, pz, S_, D_, 64, 128, true);
  fused_kernel<<<128, 384, SMEM_BYTES, cudaStreamPerThread>>>((const __nv_bfloat16*)d_in[0], (__nv_bfloat16*)d_out, (const __nv_bfloat16*)d_in[3],
                                                              (const __nv_bfloat16*)d_in[4], (const __nv_bfloat16*)d_in[5], 0u, maps);
}
```
